```python
import torch

def _softmax(x, axis=-1):
    return torch.softmax(x, dim=axis)
def _gelu(x):
    return torch.nn.functional.gelu(x, approximate="tanh")
def _silu(x):
    return torch.nn.functional.silu(x)
def _sigmoid(x):
    return torch.sigmoid(x)
def _layernorm(x, axis=-1, eps=1e-5):
    m = x.mean(dim=axis, keepdim=True)
    v = x.var(dim=axis, keepdim=True, unbiased=False)
    return (x - m) / torch.sqrt(v + eps)
def _scatter_add(tgt, idx, src, axis=0):
    return tgt.clone().index_add_(axis, idx, src)
def _segment_sum(src, seg, n):
    out = torch.zeros((n,) + src.shape[1:], dtype=src.dtype)
    return out.index_add_(0, seg, src)
def _pad(x, pw):
    flat = tuple(v for pair in reversed(pw) for v in pair)
    return torch.nn.functional.pad(x, flat)

kernel_name = 'gated_mix__softmax_full_mha__dense_activation_gelu__prompt'

def setup_inputs():

    _w = (lambda a: (lambda t: t.to(torch.bfloat16) if t.is_floating_point() else t)(torch.as_tensor(a)))
    def _A_setup():
        B, S, D = 1, 2048, 512
        return {
            "x": _w((lambda *s: torch.randn(*s, dtype=torch.bfloat16) * 0.05)(B, S, D)),
            "wqkv": _w((lambda *s: torch.randn(*s, dtype=torch.bfloat16) * 0.8)(D, 3 * D)),
            "wo": _w((lambda *s: torch.randn(*s, dtype=torch.bfloat16) * 0.05)(D, D)),
        }
    _A_in = _A_setup()

    def _B_setup():
        B, S, D, F = 1, 2048, 512, 1792
        return {
            "x": _w((lambda *s: torch.randn(*s, dtype=torch.bfloat16) * 0.05)(B, S, D)),
            "w1": _w((lambda *s: torch.randn(*s, dtype=torch.bfloat16) * 3.2)(D, F) * (D ** -0.5)),
            "b1": _w((lambda *s: torch.randn(*s, dtype=torch.bfloat16) * 3.2)(F) * 0.01),
            "w2": _w((lambda *s: torch.randn(*s, dtype=torch.bfloat16) * 0.8)(F, D) * (F ** -0.5)),
            "b2": _w((lambda *s: torch.randn(*s, dtype=torch.bfloat16) * 1.6)(D) * 0.01),
        }
    _B_in = _B_setup()

    return {
        "A_x": _A_in["x"],
        "A_wqkv": _A_in["wqkv"],
        "A_wo": _A_in["wo"],
        "B_x": _B_in["x"],
        "B_w1": _B_in["w1"],
        "B_b1": _B_in["b1"],
        "B_w2": _B_in["w2"],
        "B_b2": _B_in["b2"],
        "gate_w": _w((lambda *s: torch.randn(*s, dtype=torch.bfloat16) * 0.05)(512) * 16.0),
    }

def reference(A_x, A_wqkv, A_wo, B_x, B_w1, B_b1, B_w2, B_b2, gate_w):
    def _A_ref(x, wqkv, wo):
        B, S, D = x.shape
        H = 32; Dh = D // H
        qkv = (lambda x, *d: x.permute(*d))((x @ wqkv).reshape(B, S, 3, H, Dh), 2, 0, 3, 1, 4)
        q, k, v = qkv[0], qkv[1], qkv[2]
        scale = Dh ** -0.5
        scores = torch.einsum("bhqd,bhkd->bhqk", q, k) * scale
        p = _softmax(scores, axis=-1)
        o = torch.einsum("bhqk,bhkd->bhqd", p, v)
        return (lambda x, *d: x.permute(*d))(o, 0, 2, 1, 3).reshape(B, S, D) @ wo

    def _B_ref(x, w1, b1, w2, b2):
        h = torch.einsum("bsd,df->bsf", x, w1) + b1
        h = _gelu(h)
        return torch.einsum("bsf,fd->bsd", h, w2) + b2

    x = A_x
    g = _sigmoid((x * gate_w).sum(-1, keepdims=True))
    a = _A_ref(x, A_wqkv, A_wo)
    b = _B_ref(x, B_w1, B_b1, B_w2, B_b2)
    return g * a + (1 - g) * b
```

```cpp
#include <cuda_runtime.h>
#include <cuda_bf16.h>
#include <cuda.h>
#include <stdint.h>

namespace {

template<int TB> __device__ __forceinline__ void wgmma_rs_n24_f32_bf16(float (&d)[12], const uint32_t a0, const uint32_t a1, const uint32_t a2, const uint32_t a3, uint64_t descB, int scaleD) {
  asm volatile("{\n.reg .pred p;\nsetp.ne.b32 p, %17, 0;\nwgmma.mma_async.sync.aligned.m64n24k16.f32.bf16.bf16 {%0, %1, %2, %3, %4, %5, %6, %7, %8, %9, %10, %11}, {%12, %13, %14, %15}, %16, p, 1, 1, %18;\n}\n"
    : "+f"(d[0]), "+f"(d[1]), "+f"(d[2]), "+f"(d[3]), "+f"(d[4]), "+f"(d[5]), "+f"(d[6]), "+f"(d[7]), "+f"(d[8]), "+f"(d[9]), "+f"(d[10]), "+f"(d[11])
    : "r"(a0), "r"(a1), "r"(a2), "r"(a3), "l"(descB), "r"(scaleD), "n"(TB));
}
template<int TA, int TB> __device__ __forceinline__ void wgmma_ss_n128_f32_bf16(float (&d)[64], uint64_t descA, uint64_t descB, int scaleD) {
  asm volatile("{\n.reg .pred p;\nsetp.ne.b32 p, %66, 0;\nwgmma.mma_async.sync.aligned.m64n128k16.f32.bf16.bf16 {%0, %1, %2, %3, %4, %5, %6, %7, %8, %9, %10, %11, %12, %13, %14, %15, %16, %17, %18, %19, %20, %21, %22, %23, %24, %25, %26, %27, %28, %29, %30, %31, %32, %33, %34, %35, %36, %37, %38, %39, %40, %41, %42, %43, %44, %45, %46, %47, %48, %49, %50, %51, %52, %53, %54, %55, %56, %57, %58, %59, %60, %61, %62, %63}, %64, %65, p, 1, 1, %67, %68;\n}\n"
    : "+f"(d[0]), "+f"(d[1]), "+f"(d[2]), "+f"(d[3]), "+f"(d[4]), "+f"(d[5]), "+f"(d[6]), "+f"(d[7]), "+f"(d[8]), "+f"(d[9]), "+f"(d[10]), "+f"(d[11]), "+f"(d[12]), "+f"(d[13]), "+f"(d[14]), "+f"(d[15]), "+f"(d[16]), "+f"(d[17]), "+f"(d[18]), "+f"(d[19]), "+f"(d[20]), "+f"(d[21]), "+f"(d[22]), "+f"(d[23]), "+f"(d[24]), "+f"(d[25]), "+f"(d[26]), "+f"(d[27]), "+f"(d[28]), "+f"(d[29]), "+f"(d[30]), "+f"(d[31]), "+f"(d[32]), "+f"(d[33]), "+f"(d[34]), "+f"(d[35]), "+f"(d[36]), "+f"(d[37]), "+f"(d[38]), "+f"(d[39]), "+f"(d[40]), "+f"(d[41]), "+f"(d[42]), "+f"(d[43]), "+f"(d[44]), "+f"(d[45]), "+f"(d[46]), "+f"(d[47]), "+f"(d[48]), "+f"(d[49]), "+f"(d[50]), "+f"(d[51]), "+f"(d[52]), "+f"(d[53]), "+f"(d[54]), "+f"(d[55]), "+f"(d[56]), "+f"(d[57]), "+f"(d[58]), "+f"(d[59]), "+f"(d[60]), "+f"(d[61]), "+f"(d[62]), "+f"(d[63])
    : "l"(descA), "l"(descB), "r"(scaleD), "n"(TA), "n"(TB));
}
template<int TA, int TB> __device__ __forceinline__ void wgmma_ss_n64_f32_bf16(float (&d)[32], uint64_t descA, uint64_t descB, int scaleD) {
  asm volatile("{\n.reg .pred p;\nsetp.ne.b32 p, %34, 0;\nwgmma.mma_async.sync.aligned.m64n64k16.f32.bf16.bf16 {%0, %1, %2, %3, %4, %5, %6, %7, %8, %9, %10, %11, %12, %13, %14, %15, %16, %17, %18, %19, %20, %21, %22, %23, %24, %25, %26, %27, %28, %29, %30, %31}, %32, %33, p, 1, 1, %35, %36;\n}\n"
    : "+f"(d[0]), "+f"(d[1]), "+f"(d[2]), "+f"(d[3]), "+f"(d[4]), "+f"(d[5]), "+f"(d[6]), "+f"(d[7]), "+f"(d[8]), "+f"(d[9]), "+f"(d[10]), "+f"(d[11]), "+f"(d[12]), "+f"(d[13]), "+f"(d[14]), "+f"(d[15]), "+f"(d[16]), "+f"(d[17]), "+f"(d[18]), "+f"(d[19]), "+f"(d[20]), "+f"(d[21]), "+f"(d[22]), "+f"(d[23]), "+f"(d[24]), "+f"(d[25]), "+f"(d[26]), "+f"(d[27]), "+f"(d[28]), "+f"(d[29]), "+f"(d[30]), "+f"(d[31])
    : "l"(descA), "l"(descB), "r"(scaleD), "n"(TA), "n"(TB));
}
template<int TA, int TB> __device__ __forceinline__ void wgmma_ss_n8_f32_bf16(float (&d)[4], uint64_t descA, uint64_t descB, int scaleD) {
  asm volatile("{\n.reg .pred p;\nsetp.ne.b32 p, %6, 0;\nwgmma.mma_async.sync.aligned.m64n8k16.f32.bf16.bf16 {%0, %1, %2, %3}, %4, %5, p, 1, 1, %7, %8;\n}\n"
    : "+f"(d[0]), "+f"(d[1]), "+f"(d[2]), "+f"(d[3])
    : "l"(descA), "l"(descB), "r"(scaleD), "n"(TA), "n"(TB));
}
template<int TA, int TB> __device__ __forceinline__ void wgmma_ss_n96_f32_bf16(float (&d)[48], uint64_t descA, uint64_t descB, int scaleD) {
  asm volatile("{\n.reg .pred p;\nsetp.ne.b32 p, %50, 0;\nwgmma.mma_async.sync.aligned.m64n96k16.f32.bf16.bf16 {%0, %1, %2, %3, %4, %5, %6, %7, %8, %9, %10, %11, %12, %13, %14, %15, %16, %17, %18, %19, %20, %21, %22, %23, %24, %25, %26, %27, %28, %29, %30, %31, %32, %33, %34, %35, %36, %37, %38, %39, %40, %41, %42, %43, %44, %45, %46, %47}, %48, %49, p, 1, 1, %51, %52;\n}\n"
    : "+f"(d[0]), "+f"(d[1]), "+f"(d[2]), "+f"(d[3]), "+f"(d[4]), "+f"(d[5]), "+f"(d[6]), "+f"(d[7]), "+f"(d[8]), "+f"(d[9]), "+f"(d[10]), "+f"(d[11]), "+f"(d[12]), "+f"(d[13]), "+f"(d[14]), "+f"(d[15]), "+f"(d[16]), "+f"(d[17]), "+f"(d[18]), "+f"(d[19]), "+f"(d[20]), "+f"(d[21]), "+f"(d[22]), "+f"(d[23]), "+f"(d[24]), "+f"(d[25]), "+f"(d[26]), "+f"(d[27]), "+f"(d[28]), "+f"(d[29]), "+f"(d[30]), "+f"(d[31]), "+f"(d[32]), "+f"(d[33]), "+f"(d[34]), "+f"(d[35]), "+f"(d[36]), "+f"(d[37]), "+f"(d[38]), "+f"(d[39]), "+f"(d[40]), "+f"(d[41]), "+f"(d[42]), "+f"(d[43]), "+f"(d[44]), "+f"(d[45]), "+f"(d[46]), "+f"(d[47])
    : "l"(descA), "l"(descB), "r"(scaleD), "n"(TA), "n"(TB));
}
template<int TB> __device__ __forceinline__ void wgmmaz_rs_n16_f16_f16(uint32_t (&d)[4], const uint32_t a0, const uint32_t a1, const uint32_t a2, const uint32_t a3, uint64_t descB) {
  asm volatile("wgmma.mma_async.sync.aligned.m64n16k16.f16.f16.f16 {%0, %1, %2, %3}, {%4, %5, %6, %7}, %8, 0, 1, 1, %9;\n"
    : "=r"(d[0]), "=r"(d[1]), "=r"(d[2]), "=r"(d[3])
    : "r"(a0), "r"(a1), "r"(a2), "r"(a3), "l"(descB), "n"(TB));
}
template<int TB> __device__ __forceinline__ void wgmmaz_rs_n16_f32_f16(float (&d)[8], const uint32_t a0, const uint32_t a1, const uint32_t a2, const uint32_t a3, uint64_t descB) {
  asm volatile("wgmma.mma_async.sync.aligned.m64n16k16.f32.f16.f16 {%0, %1, %2, %3, %4, %5, %6, %7}, {%8, %9, %10, %11}, %12, 0, 1, 1, %13;\n"
    : "=f"(d[0]), "=f"(d[1]), "=f"(d[2]), "=f"(d[3]), "=f"(d[4]), "=f"(d[5]), "=f"(d[6]), "=f"(d[7])
    : "r"(a0), "r"(a1), "r"(a2), "r"(a3), "l"(descB), "n"(TB));
}
template<int TB> __device__ __forceinline__ void wgmmaz_rs_n32_f16_f16(uint32_t (&d)[8], const uint32_t a0, const uint32_t a1, const uint32_t a2, const uint32_t a3, uint64_t descB) {
  asm volatile("wgmma.mma_async.sync.aligned.m64n32k16.f16.f16.f16 {%0, %1, %2, %3, %4, %5, %6, %7}, {%8, %9, %10, %11}, %12, 0, 1, 1, %13;\n"
    : "=r"(d[0]), "=r"(d[1]), "=r"(d[2]), "=r"(d[3]), "=r"(d[4]), "=r"(d[5]), "=r"(d[6]), "=r"(d[7])
    : "r"(a0), "r"(a1), "r"(a2), "r"(a3), "l"(descB), "n"(TB));
}
template<int TB> __device__ __forceinline__ void wgmmaz_rs_n32_f32_bf16(float (&d)[16], const uint32_t a0, const uint32_t a1, const uint32_t a2, const uint32_t a3, uint64_t descB) {
  asm volatile("wgmma.mma_async.sync.aligned.m64n32k16.f32.bf16.bf16 {%0, %1, %2, %3, %4, %5, %6, %7, %8, %9, %10, %11, %12, %13, %14, %15}, {%16, %17, %18, %19}, %20, 0, 1, 1, %21;\n"
    : "=f"(d[0]), "=f"(d[1]), "=f"(d[2]), "=f"(d[3]), "=f"(d[4]), "=f"(d[5]), "=f"(d[6]), "=f"(d[7]), "=f"(d[8]), "=f"(d[9]), "=f"(d[10]), "=f"(d[11]), "=f"(d[12]), "=f"(d[13]), "=f"(d[14]), "=f"(d[15])
    : "r"(a0), "r"(a1), "r"(a2), "r"(a3), "l"(descB), "n"(TB));
}
template<int TB> __device__ __forceinline__ void wgmmaz_rs_n32_f32_f16(float (&d)[16], const uint32_t a0, const uint32_t a1, const uint32_t a2, const uint32_t a3, uint64_t descB) {
  asm volatile("wgmma.mma_async.sync.aligned.m64n32k16.f32.f16.f16 {%0, %1, %2, %3, %4, %5, %6, %7, %8, %9, %10, %11, %12, %13, %14, %15}, {%16, %17, %18, %19}, %20, 0, 1, 1, %21;\n"
    : "=f"(d[0]), "=f"(d[1]), "=f"(d[2]), "=f"(d[3]), "=f"(d[4]), "=f"(d[5]), "=f"(d[6]), "=f"(d[7]), "=f"(d[8]), "=f"(d[9]), "=f"(d[10]), "=f"(d[11]), "=f"(d[12]), "=f"(d[13]), "=f"(d[14]), "=f"(d[15])
    : "r"(a0), "r"(a1), "r"(a2), "r"(a3), "l"(descB), "n"(TB));
}
template<int TB> __device__ __forceinline__ void wgmmaz_rs_n48_f16_f16(uint32_t (&d)[12], const uint32_t a0, const uint32_t a1, const uint32_t a2, const uint32_t a3, uint64_t descB) {
  asm volatile("wgmma.mma_async.sync.aligned.m64n48k16.f16.f16.f16 {%0, %1, %2, %3, %4, %5, %6, %7, %8, %9, %10, %11}, {%12, %13, %14, %15}, %16, 0, 1, 1, %17;\n"
    : "=r"(d[0]), "=r"(d[1]), "=r"(d[2]), "=r"(d[3]), "=r"(d[4]), "=r"(d[5]), "=r"(d[6]), "=r"(d[7]), "=r"(d[8]), "=r"(d[9]), "=r"(d[10]), "=r"(d[11])
    : "r"(a0), "r"(a1), "r"(a2), "r"(a3), "l"(descB), "n"(TB));
}
template<int TB> __device__ __forceinline__ void wgmmaz_rs_n48_f32_f16(float (&d)[24], const uint32_t a0, const uint32_t a1, const uint32_t a2, const uint32_t a3, uint64_t descB) {
  asm volatile("wgmma.mma_async.sync.aligned.m64n48k16.f32.f16.f16 {%0, %1, %2, %3, %4, %5, %6, %7, %8, %9, %10, %11, %12, %13, %14, %15, %16, %17, %18, %19, %20, %21, %22, %23}, {%24, %25, %26, %27}, %28, 0, 1, 1, %29;\n"
    : "=f"(d[0]), "=f"(d[1]), "=f"(d[2]), "=f"(d[3]), "=f"(d[4]), "=f"(d[5]), "=f"(d[6]), "=f"(d[7]), "=f"(d[8]), "=f"(d[9]), "=f"(d[10]), "=f"(d[11]), "=f"(d[12]), "=f"(d[13]), "=f"(d[14]), "=f"(d[15]), "=f"(d[16]), "=f"(d[17]), "=f"(d[18]), "=f"(d[19]), "=f"(d[20]), "=f"(d[21]), "=f"(d[22]), "=f"(d[23])
    : "r"(a0), "r"(a1), "r"(a2), "r"(a3), "l"(descB), "n"(TB));
}

constexpr int NCTA = 128;
constexpr int NTHREADS = 640;

constexpr uint32_t SBC = 1024;
constexpr uint32_t SM_K = 0;
constexpr uint32_t SM_V = 65536;
constexpr uint32_t SM_R = 131072;
constexpr uint32_t SM_ONES = 229376;
constexpr uint32_t SM_GW = 230400;
constexpr uint32_t SM_B1 = SM_GW + 128;
constexpr uint32_t SM_FLAG = SM_GW + 640;
constexpr uint32_t SM_BAR = SM_GW + 1024;
constexpr int STEP = 80, NM = 32;
constexpr int NP = STEP - NM, NG = STEP / 16, NFULL = 2048 / STEP, REM = 2048 - NFULL * STEP;
static_assert(REM == 0 || REM == STEP - 32, "the short step drops one group of each kind");
constexpr uint32_t SM_TOTAL = 232448;

constexpr int B_XF = 0;
constexpr int B_AF = 8;
constexpr int B_AE = 12;
constexpr int B_BF = 16;
constexpr int B_B2F = 22;
constexpr int B_CF = 28;
constexpr int B_OF = 32;
constexpr int B_WO = 36;
constexpr int B_GATE = 37;
constexpr int B_BE = 38;
constexpr int B_ATT = 44;
constexpr int B_SH = 45;
constexpr int B_SQ = 46;
constexpr int B_P1 = 47;
constexpr int B_T = 48;
constexpr int B_M0 = 52;
constexpr int NBAR = 53;
__device__ __forceinline__ uint32_t bar_count(int i) { return i < B_AE ? 1 : i < B_BF ? 16 : i < B_BE ? 1 : i < B_T ? 16 : 4; }

__device__ __align__(1024) uint8_t g_q16[32 * 65536];
__device__ __align__(1024) uint8_t g_kv[32 * 131072];
__device__ __align__(1024) uint8_t g_o[16 * 65536];
__device__ __align__(1024) uint8_t g_o1[16 * 65536];
__device__ __align__(1024) uint8_t g_h[16 * 28 * 16384];
__device__ float g_gl[16 * 8 * 128];
__device__ uint32_t g_stat[8 * 3 * 128];
__device__ uint32_t g_cnt[28 * 32];
__device__ uint32_t g_epoch[NCTA];

constexpr uint32_t CNT_QKV = 16, CNT_H = 8, CNT_O = 32;

__device__ __forceinline__ void wg_fence() { asm volatile("wgmma.fence.sync.aligned;" ::: "memory"); }
__device__ __forceinline__ void wg_commit() { asm volatile("wgmma.commit_group.sync.aligned;" ::: "memory"); }
template <int N> __device__ __forceinline__ void wg_wait() { asm volatile("wgmma.wait_group.sync.aligned %0;" ::"n"(N) : "memory"); }
template <int N> __device__ __forceinline__ void fop(float (&a)[N]) {
#pragma unroll
  for (int i = 0; i < N; i++) asm volatile("" : "+f"(a[i])::"memory");
}
template <int N> __device__ __forceinline__ void fop(uint32_t (&a)[N]) {
#pragma unroll
  for (int i = 0; i < N; i++) asm volatile("" : "+r"(a[i])::"memory");
}
__device__ __forceinline__ uint64_t mkdesc(uint32_t addr, uint32_t lbo, uint32_t sbo, uint32_t sw) {
  return (uint64_t)((addr & 0x3FFFF) >> 4) | ((uint64_t)(lbo >> 4) << 16) | ((uint64_t)(sbo >> 4) << 32) | ((uint64_t)sw << 62);
}
__device__ __forceinline__ uint64_t mk64(uint32_t lo, uint32_t hi) { uint64_t d; asm("mov.b64 %0, {%1, %2};" : "=l"(d) : "r"(lo), "r"(hi)); return d; }
__device__ __forceinline__ void mbar_init(uint32_t a, uint32_t c) { asm volatile("mbarrier.init.shared::cta.b64 [%0], %1;" ::"r"(a), "r"(c) : "memory"); }
__device__ __forceinline__ void mbar_expect(uint32_t a, uint32_t bytes) { asm volatile("mbarrier.arrive.expect_tx.shared::cta.b64 _, [%0], %1;" ::"r"(a), "r"(bytes) : "memory"); }
__device__ __forceinline__ void mbar_arrive(uint32_t a) { asm volatile("mbarrier.arrive.shared::cta.b64 _, [%0];" ::"r"(a) : "memory"); }
__device__ __forceinline__ void mbar_wait(uint32_t a, uint32_t ph) {
  asm volatile(
      "{\n.reg .pred p;\n.reg .u32 n;\nmov.u32 n, 0;\n"
      "W0:\nmbarrier.try_wait.parity.shared::cta.b64 p, [%0], %1, 2000;\n@p bra W1;\n"
      "add.u32 n, n, 1;\nsetp.lt.u32 p, n, 0x200000;\n@p bra W0;\ntrap;\nW1:\n}" ::"r"(a), "r"(ph) : "memory");
}
__device__ __forceinline__ void mbar_spin(uint32_t a, uint32_t ph) {
  asm volatile(
      "{\n.reg .pred p;\n.reg .u32 n;\nmov.u32 n, 0;\n"
      "W0:\nmbarrier.try_wait.parity.shared::cta.b64 p, [%0], %1;\n@p bra W1;\n"
      "add.u32 n, n, 1;\nsetp.lt.u32 p, n, 0x1000000;\n@p bra W0;\ntrap;\nW1:\n}" ::"r"(a), "r"(ph) : "memory");
}
__device__ __forceinline__ void tma2d(uint32_t dst, const CUtensorMap* m, int c0, int c1, uint32_t bar) {
  asm volatile("cp.async.bulk.tensor.2d.shared::cluster.global.mbarrier::complete_tx::bytes [%0], [%1, {%3, %4}], [%2];"
               ::"r"(dst), "l"(m), "r"(bar), "r"(c0), "r"(c1) : "memory");
}
__device__ __forceinline__ void tma5d(uint32_t dst, const CUtensorMap* m, int c0, int c4, uint32_t bar) {
  asm volatile("cp.async.bulk.tensor.5d.shared::cluster.global.mbarrier::complete_tx::bytes [%0], [%1, {%3, %5, %5, %5, %4}], [%2];"
               ::"r"(dst), "l"(m), "r"(bar), "r"(c0), "r"(c4), "r"(0) : "memory");
}
__device__ __forceinline__ void tma3d(uint32_t dst, const CUtensorMap* m, int c0, int c1, int c2, uint32_t bar) {
  asm volatile("cp.async.bulk.tensor.3d.shared::cluster.global.mbarrier::complete_tx::bytes [%0], [%1, {%3, %4, %5}], [%2];"
               ::"r"(dst), "l"(m), "r"(bar), "r"(c0), "r"(c1), "r"(c2) : "memory");
}
__device__ __forceinline__ void tma3d_mc(uint32_t dst, const CUtensorMap* m, int c0, int c1, int c2, uint32_t bar) {
  asm volatile("cp.async.bulk.tensor.3d.shared::cluster.global.mbarrier::complete_tx::bytes.multicast::cluster [%0], [%1, {%3, %4, %5}], [%2], %6;"
               ::"r"(dst), "l"(m), "r"(bar), "r"(c0), "r"(c1), "r"(c2), "h"((uint16_t)3) : "memory");
}
__device__ __forceinline__ void bulk1d_mc(uint32_t dst, const void* src, uint32_t bytes, uint32_t bar) {
  asm volatile("cp.async.bulk.shared::cluster.global.mbarrier::complete_tx::bytes.multicast::cluster [%0], [%1], %2, [%3], %4;"
               ::"r"(dst), "l"(src), "r"(bytes), "r"(bar), "h"((uint16_t)3) : "memory");
}
__device__ __forceinline__ void mbar_arrive_pair(uint32_t a, int lane) {
  if (lane < 2) asm volatile("{\n.reg .b32 ra;\nmapa.shared::cluster.u32 ra, %0, %1;\nmbarrier.arrive.shared::cluster.b64 _, [ra];\n}" ::"r"(a), "r"(lane) : "memory");
}
__device__ __forceinline__ void bulk1d(uint32_t dst, const void* src, uint32_t bytes, uint32_t bar) {
  asm volatile("cp.async.bulk.shared::cluster.global.mbarrier::complete_tx::bytes [%0], [%1], %2, [%3];"
               ::"r"(dst), "l"(src), "r"(bytes), "r"(bar) : "memory");
}
__device__ __forceinline__ bool elect() {
  uint32_t p;
  asm volatile("{\n.reg .pred p;\nelect.sync _|p, 0xffffffff;\nselp.u32 %0, 1, 0, p;\n}" : "=r"(p));
  return p != 0;
}
__device__ __forceinline__ void l2_prefetch(const void* p, uint32_t bytes) {
  asm volatile("cp.async.bulk.prefetch.L2.global [%0], %1;" ::"l"(p), "r"(bytes) : "memory");
}
__device__ __forceinline__ void fence_async_smem() { asm volatile("fence.proxy.async.shared::cta;" ::: "memory"); }
__device__ __forceinline__ void fence_async_gmem() { asm volatile("fence.proxy.async.global;" ::: "memory"); }
__device__ __forceinline__ void named_arrive(int id, int n) { asm volatile("bar.arrive %0, %1;" ::"r"(id), "r"(n) : "memory"); }
__device__ __forceinline__ void named_sync(int id, int n) { asm volatile("bar.sync %0, %1;" ::"r"(id), "r"(n) : "memory"); }
__device__ __forceinline__ void cnt_bump(uint32_t* cnt) {
  asm volatile("fence.acq_rel.gpu;" ::: "memory");
  asm volatile("red.relaxed.gpu.global.add.u32 [%0], 1;" ::"l"(cnt) : "memory");
}
__device__ __forceinline__ void cnt_wait(const uint32_t* cnt, uint32_t target) {
  uint32_t n = 0;
  while (true) {
    uint32_t v;
    asm volatile("ld.acquire.gpu.global.u32 %0, [%1];" : "=r"(v) : "l"(cnt) : "memory");
    if ((int32_t)(v - target) >= 0) break;
    if (++n > (1u << 21)) __trap();
    __nanosleep(40);
  }
}
__device__ __forceinline__ uint32_t ldcg32(const void* p) { uint32_t v; asm volatile("ld.global.cg.u32 %0, [%1];" : "=r"(v) : "l"(p) : "memory"); return v; }
__device__ __forceinline__ void stg32(void* p, uint32_t v) { asm volatile("st.global.u32 [%0], %1;" ::"l"(p), "r"(v) : "memory"); }
__device__ __forceinline__ uint32_t lds32(uint32_t a) { uint32_t v; asm volatile("ld.shared.u32 %0, [%1];" : "=r"(v) : "r"(a) : "memory"); return v; }
__device__ __forceinline__ float2 lds64f(uint32_t a) { float2 v; asm volatile("ld.shared.v2.f32 {%0,%1}, [%2];" : "=f"(v.x), "=f"(v.y) : "r"(a) : "memory"); return v; }
__device__ __forceinline__ void sts32(uint32_t a, uint32_t v) { asm volatile("st.shared.u32 [%0], %1;" ::"r"(a), "r"(v) : "memory"); }
__device__ __forceinline__ uint32_t hadd2(uint32_t a, uint32_t b) { uint32_t d; asm("add.rn.f16x2 %0, %1, %2;" : "=r"(d) : "r"(a), "r"(b)); return d; }
__device__ __forceinline__ uint32_t hfma2(uint32_t a, uint32_t b, uint32_t c) { uint32_t d; asm("fma.rn.f16x2 %0, %1, %2, %3;" : "=r"(d) : "r"(a), "r"(b), "r"(c)); return d; }
__device__ __forceinline__ float ex2(float x) { float y; asm("ex2.approx.ftz.f32 %0, %1;" : "=f"(y) : "f"(x)); return y; }
__device__ __forceinline__ float rcp(float x) { float y; asm("rcp.approx.ftz.f32 %0, %1;" : "=f"(y) : "f"(x)); return y; }
__device__ __forceinline__ float tanh_(float x) { float y; asm("tanh.approx.f32 %0, %1;" : "=f"(y) : "f"(x)); return y; }
__device__ __forceinline__ uint32_t packbf(float lo, float hi) { uint32_t d; asm("cvt.rn.bf16x2.f32 %0, %1, %2;" : "=r"(d) : "f"(hi), "f"(lo)); return d; }
__device__ __forceinline__ uint32_t packhf(float lo, float hi) { uint32_t d; asm("cvt.rn.f16x2.f32 %0, %1, %2;" : "=r"(d) : "f"(hi), "f"(lo)); return d; }
__device__ __forceinline__ float bflo(uint32_t v) { return __uint_as_float(v << 16); }
__device__ __forceinline__ float bfhi(uint32_t v) { return __uint_as_float(v & 0xFFFF0000u); }

constexpr float QSCALE = 0.25f * 1.4426950408889634f;
constexpr float VSCALE = 181.0f / 128.0f / 4096.0f;
constexpr float LOG2_VSCALE = 0.49984588708320537f - 12.0f;
constexpr float KSCALE = 35.0f / 16.0f;

__device__ __forceinline__ uint32_t poly_exp2(uint32_t xh, uint32_t& t, uint32_t c1, uint32_t c2) {
  t = hfma2(xh, c1, 0x65A565A5u);
  const uint32_t g = hadd2(xh, hfma2(t, c2, 0x6A2E6A2Eu));
  return hfma2(hfma2(g, g, 0x4F494F49u), g, 0x668C668Du);
}
__host__ __device__ constexpr bool is_mufu(int j16, int half) {
  return 2 * (j16 < NFULL * NG ? j16 % NG : j16 - NFULL * NG + 1) + half < NM / 8;
}
constexpr uint32_t KV_HI = 16u | (3u << 30);
__host__ __device__ constexpr uint32_t v_lo(int j16) {
  return ((SBC + SM_V + j16 * 512) >> 4) | ((SM_ONES - SM_V - j16 * 512 + (is_mufu(j16, 1) ? 0 : is_mufu(j16, 0) ? 256 : 512)) << 12);
}
__device__ __forceinline__ uint32_t poly_join(uint32_t u, uint32_t t) { return __funnelshift_l(t, t, 7) + u; }
__device__ __forceinline__ float gelu2(float x) {
  const float in = x * fmaf(x * x, 0.044715f * 0.7978845608028654f, 0.7978845608028654f);
  return fmaf(x, tanh_(in), x);
}
__device__ __forceinline__ float clampz(float z) { return z < -40.f ? -40.f : z; }
__device__ __forceinline__ uint32_t xslab(uint32_t sb, int i) { return sb + i * 16384; }
__device__ __forceinline__ int f1_order(int i) { return (0x73625140u >> (4 * i)) & 7; }

struct Params {
  const __nv_bfloat16* x;
  const __nv_bfloat16* wqkv;
  const __nv_bfloat16* w1;
  const __nv_bfloat16* w2;
  const __nv_bfloat16* wo;
  const __nv_bfloat16* b1;
  const __nv_bfloat16* b2;
  const __nv_bfloat16* gate_w;
  __nv_bfloat16* out;
};

template <bool ISQ>
__device__ __forceinline__ uint32_t qk_pack(const float* d, uint32_t* pk, float k0, float k1) {
  float a[8];
#pragma unroll
  for (int i = 0; i < 8; i++) a[i] = ISQ ? d[i] * QSCALE : d[i];
#pragma unroll
  for (int i = 0; i < 4; i++) {
    const float s = (i & 1) ? k1 : k0;
    pk[i] = ISQ ? packhf(a[2 * i], a[2 * i + 1]) : packhf(a[2 * i] * s, a[2 * i + 1] * s);
  }
  float s0 = a[0] * a[0] + a[1] * a[1] + a[4] * a[4] + a[5] * a[5];
  float s1 = a[2] * a[2] + a[3] * a[3] + a[6] * a[6] + a[7] * a[7];
  s0 += __shfl_xor_sync(0xffffffffu, s0, 1);
  s1 += __shfl_xor_sync(0xffffffffu, s1, 1);
  s0 += __shfl_xor_sync(0xffffffffu, s0, 2);
  s1 += __shfl_xor_sync(0xffffffffu, s1, 2);
  return max(__float_as_uint(s0), __float_as_uint(s1));
}
__device__ __forceinline__ void row_store(uint8_t* p, const uint32_t* pk) {
  *(uint2*)p = make_uint2(pk[0], pk[2]);
  *(uint2*)(p + 256) = make_uint2(pk[1], pk[3]);
}

template <int NACC>
__device__ __forceinline__ void bias_init(float (&acc)[NACC], uint32_t sb1, int lane) {
#pragma unroll
  for (int j = 0; j < NACC / 4; j++) {
    const uint32_t bb = lds32(sb1 + j * 16 + (lane & 3) * 4);
    acc[4 * j] = acc[4 * j + 2] = bflo(bb);
    acc[4 * j + 1] = acc[4 * j + 3] = bfhi(bb);
  }
}
template <int NACC>
__device__ __forceinline__ void gelu_pack(const float (&acc)[NACC], uint32_t (&r)[NACC / 2]) {
#pragma unroll
  for (int e = 0; e < NACC / 2; e++) r[e] = packbf(gelu2(acc[2 * e]), gelu2(acc[2 * e + 1]));
}
template <int NR>
__device__ __forceinline__ void h_stage(const uint32_t (&r)[NR], uint32_t dst) {
#pragma unroll
  for (int j = 0; j < NR / 4; j++)
    asm volatile("stmatrix.sync.aligned.m8n8.x4.shared.b16 [%0], {%1,%2,%3,%4};" ::"r"(dst + (j >> 1) * 8192 + (j & 1) * 256),
                 "r"(r[4 * j]), "r"(r[4 * j + 1]), "r"(r[4 * j + 2]), "r"(r[4 * j + 3]) : "memory");
}

__device__ __forceinline__ void out_store(const float (&a)[32], uint32_t sg, uint32_t stg, uint8_t* dst, int lane) {
#pragma unroll
  for (int j = 0; j < 4; j++) {
    const float2 g0 = lds64f(sg + (j * 16 + (lane & 3) * 2) * 4), g1 = lds64f(sg + (j * 16 + 8 + (lane & 3) * 2) * 4);
    asm volatile("stmatrix.sync.aligned.m8n8.x4.trans.shared.b16 [%0], {%1,%2,%3,%4};" ::"r"(stg + j * 512 + lane * 16),
                 "r"(packbf(a[8 * j] * g0.x, a[8 * j + 1] * g0.y)), "r"(packbf(a[8 * j + 2] * g0.x, a[8 * j + 3] * g0.y)),
                 "r"(packbf(a[8 * j + 4] * g1.x, a[8 * j + 5] * g1.y)), "r"(packbf(a[8 * j + 6] * g1.x, a[8 * j + 7] * g1.y)) : "memory");
  }
  __syncwarp();
#pragma unroll
  for (int j = 0; j < 4; j++) {
    uint4 v;
    asm volatile("ld.shared.v4.u32 {%0,%1,%2,%3}, [%4];" : "=r"(v.x), "=r"(v.y), "=r"(v.z), "=r"(v.w) : "r"(stg + j * 512 + lane * 16) : "memory");
    *(uint4*)(dst + (j * 16 + (lane >> 4) * 8 + (lane & 7)) * 1024 + ((lane >> 3) & 1) * 16) = v;
  }
  __syncwarp();
}
template <bool B> struct BoolC { static constexpr bool value = B; };
template <int N> struct QK;
template <> struct QK<16> {
  static __device__ __forceinline__ void f32(float (&d)[8], const uint32_t (&q)[4], uint64_t b) { wgmmaz_rs_n16_f32_f16<0>(d, q[0], q[1], q[2], q[3], b); }
  static __device__ __forceinline__ void f16(uint32_t (&d)[4], const uint32_t (&q)[4], uint64_t b) { wgmmaz_rs_n16_f16_f16<0>(d, q[0], q[1], q[2], q[3], b); }
};
template <> struct QK<32> {
  static __device__ __forceinline__ void f32(float (&d)[16], const uint32_t (&q)[4], uint64_t b) { wgmmaz_rs_n32_f32_f16<0>(d, q[0], q[1], q[2], q[3], b); }
  static __device__ __forceinline__ void f16(uint32_t (&d)[8], const uint32_t (&q)[4], uint64_t b) { wgmmaz_rs_n32_f16_f16<0>(d, q[0], q[1], q[2], q[3], b); }
};
template <> struct QK<48> {
  static __device__ __forceinline__ void f32(float (&d)[24], const uint32_t (&q)[4], uint64_t b) { wgmmaz_rs_n48_f32_f16<0>(d, q[0], q[1], q[2], q[3], b); }
  static __device__ __forceinline__ void f16(uint32_t (&d)[12], const uint32_t (&q)[4], uint64_t b) { wgmmaz_rs_n48_f16_f16<0>(d, q[0], q[1], q[2], q[3], b); }
};
#define SEED1 118
#define SEED2 130
#define CM1 0xa9d
#define CM2 0x8c7
template <int N> struct Perm {
  int v[N];
  __host__ __device__ constexpr Perm(unsigned s) : v{} {
    for (int i = 0; i < N; i++) v[i] = i;
    if (s) for (int i = N - 1; i > 0; i--) { s = s * 1664525u + 1013904223u; const int j = (s >> 16) % (i + 1); const int t = v[i]; v[i] = v[j]; v[j] = t; }
  }
};
template <int M, int PL, int GP, int J16, bool OVERLAP = false, unsigned SEED = 0, unsigned cm = 0x555>
__device__ __forceinline__ void att_step(float (&O)[12], uint32_t (&P)[STEP / 4], const uint32_t (&q)[4], uint64_t d, int64_t koff,
                                         const uint32_t (&cc)[4]) {
  float Sm[M ? M / 2 : 1];
  uint32_t Sp[PL / 4];
  wg_fence();
  if constexpr (M != 0) {
    QK<PL>::f16(Sp, q, d + koff + 2 * M);
    QK<M>::f32(Sm, q, d + koff);
    wg_commit();
  }
  if constexpr (GP != 0) {
#pragma unroll
    for (int g = 0; g < GP; g++)
      wgmma_rs_n24_f32_bf16<1>(O, P[4 * g], P[4 * g + 1], P[4 * g + 2], P[4 * g + 3], d + ((int64_t)v_lo(J16 + g) - (int64_t)v_lo(J16)), 1);
    wg_commit();
  }
  if constexpr (M != 0) {
    float E[M / 2];
    uint32_t U[PL / 4], T[PL / 4];
    wg_wait<OVERLAP ? 1 : 0>();
    fop(Sm); fop(Sp);
    constexpr Perm<M / 2 + PL / 4> p1(OVERLAP ? SEED : 0);
    constexpr Perm<M / 4 + PL / 4> p2(OVERLAP ? SEED * 7 : 0);
#pragma unroll
    for (int n = 0; n < M / 2 + PL / 4; n++) {
      const int i = p1.v[n];
      if (i < M / 2) E[i] = ex2(Sm[i]);
      else U[i - M / 2] = poly_exp2(Sp[i - M / 2], T[i - M / 2], cc[((i - M / 2) & 1) ^ 1], cc[2 + ((cm >> (i - M / 2)) & 1)]);
    }
    if (OVERLAP) wg_wait<0>();
#pragma unroll
    for (int n = 0; n < M / 4 + PL / 4; n++) {
      const int i = p2.v[n];
      P[i] = i < M / 4 ? packbf(E[2 * i], E[2 * i + 1]) : poly_join(U[i - M / 4], T[i - M / 4]);
    }
    fop(P);
  } else {
    wg_wait<0>();
  }
}

__device__ __forceinline__ void slow_k(uint32_t sb, const Params& prm, int head) {
  for (int s = 0; s < 2; s++) mbar_wait(sb + SM_BAR + 8 * (B_XF + s), 1);
#pragma unroll 1
  for (int key = threadIdx.x; key < 2048; key += 512) {
    float a[16];
#pragma unroll
    for (int i = 0; i < 16; i++) a[i] = 0.f;
#pragma unroll 1
    for (int k = 0; k < 512; k++) {
      const float xv = __bfloat162float(prm.x[key * 512 + k]);
      const uint32_t* w = (const uint32_t*)(prm.wqkv + k * 1536 + 512 + head * 16);
#pragma unroll
      for (int i = 0; i < 8; i++) { const uint32_t u = w[i]; a[2 * i] = fmaf(xv, bflo(u), a[2 * i]); a[2 * i + 1] = fmaf(xv, bfhi(u), a[2 * i + 1]); }
    }
#pragma unroll
    for (int i = 0; i < 8; i++) sts32(sb + SM_K + (key >> 3) * 256 + (i >> 2) * 128 + (key & 7) * 16 + (i & 3) * 4, packbf(a[2 * i], a[2 * i + 1]));
  }
  fence_async_smem();
  named_sync(3, 512);
}
__device__ __forceinline__ void attn_slow(uint32_t sb, const Params& prm, int head, int row, float (&Oout)[12]) {
  uint32_t q[4];
  {
    float a[8];
#pragma unroll
    for (int i = 0; i < 8; i++) a[i] = 0.f;
#pragma unroll 1
    for (int k = 0; k < 512; k++) {
      const float x0 = __bfloat162float(prm.x[row * 512 + k]), x1 = __bfloat162float(prm.x[(row + 8) * 512 + k]);
      const uint32_t* w = (const uint32_t*)(prm.wqkv + k * 1536 + head * 16) + (threadIdx.x & 3);
      const uint32_t u0 = w[0], u1 = w[4];
      a[0] = fmaf(x0, bflo(u0), a[0]); a[1] = fmaf(x0, bfhi(u0), a[1]); a[2] = fmaf(x1, bflo(u0), a[2]); a[3] = fmaf(x1, bfhi(u0), a[3]);
      a[4] = fmaf(x0, bflo(u1), a[4]); a[5] = fmaf(x0, bfhi(u1), a[5]); a[6] = fmaf(x1, bflo(u1), a[6]); a[7] = fmaf(x1, bfhi(u1), a[7]);
    }
#pragma unroll
    for (int i = 0; i < 4; i++) q[i] = packbf(a[2 * i], a[2 * i + 1]);
  }
  float O[12];
#pragma unroll
  for (int i = 0; i < 12; i++) O[i] = 0.f;
  float m0 = -INFINITY, m1 = -INFINITY;
  uint64_t dK = mkdesc(SBC + SM_K, 128, 256, 0);
#pragma unroll 1
  for (int j = 0; j < 64; j++) {
    const uint64_t dV0 = mk64(v_lo(2 * j), KV_HI), dV1 = mk64(v_lo(2 * j + 1), KV_HI);
    float Sx[16];
    wg_fence();
    wgmmaz_rs_n32_f32_bf16<0>(Sx, q[0], q[1], q[2], q[3], dK);
    wg_commit();
    wg_wait<0>();
    fop(Sx);
    float x0 = m0, x1 = m1;
#pragma unroll
    for (int i = 0; i < 4; i++) {
      const uint32_t u0 = packbf(Sx[4 * i], Sx[4 * i + 1]), u1 = packbf(Sx[4 * i + 2], Sx[4 * i + 3]);
      Sx[4 * i] = bflo(u0) * QSCALE; Sx[4 * i + 1] = bfhi(u0) * QSCALE; Sx[4 * i + 2] = bflo(u1) * QSCALE; Sx[4 * i + 3] = bfhi(u1) * QSCALE;
      x0 = fmaxf(x0, fmaxf(Sx[4 * i], Sx[4 * i + 1]));
      x1 = fmaxf(x1, fmaxf(Sx[4 * i + 2], Sx[4 * i + 3]));
    }
    x0 = fmaxf(x0, __shfl_xor_sync(0xffffffffu, x0, 1)); x0 = fmaxf(x0, __shfl_xor_sync(0xffffffffu, x0, 2));
    x1 = fmaxf(x1, __shfl_xor_sync(0xffffffffu, x1, 1)); x1 = fmaxf(x1, __shfl_xor_sync(0xffffffffu, x1, 2));
    float r0 = (x0 == m0) ? 1.f : ex2(m0 - x0), r1 = (x1 == m1) ? 1.f : ex2(m1 - x1);
    m0 = x0; m1 = x1;
#pragma unroll
    for (int i = 0; i < 3; i++) { O[4 * i] *= r0; O[4 * i + 1] *= r0; O[4 * i + 2] *= r1; O[4 * i + 3] *= r1; }
    uint32_t P[8];
#pragma unroll
    for (int i = 0; i < 4; i++) {
      const float o = is_mufu(2 * j + (i >> 1), i & 1) ? 0.f : LOG2_VSCALE;
      P[2 * i] = packbf(ex2(Sx[4 * i] - m0 + o), ex2(Sx[4 * i + 1] - m0 + o));
      P[2 * i + 1] = packbf(ex2(Sx[4 * i + 2] - m1 + o), ex2(Sx[4 * i + 3] - m1 + o));
    }
    fop(O);
    wg_fence();
    wgmma_rs_n24_f32_bf16<1>(O, P[0], P[1], P[2], P[3], dV0, 1);
    wgmma_rs_n24_f32_bf16<1>(O, P[4], P[5], P[6], P[7], dV1, 1);
    wg_commit();
    wg_wait<0>();
    fop(O);
    dK += 64;
  }
#pragma unroll
  for (int i = 0; i < 12; i++) Oout[i] = O[i];
}

__global__ void __cluster_dims__(2, 1, 1) __launch_bounds__(NTHREADS, 1)
fused_kernel(const __grid_constant__ CUtensorMap tm_x, const __grid_constant__ CUtensorMap tm_wqkv,
             const __grid_constant__ CUtensorMap tm_w1a, const __grid_constant__ CUtensorMap tm_w1b, const __grid_constant__ CUtensorMap tm_w2,
             const __grid_constant__ CUtensorMap tm_wo, const Params prm) {
  extern __shared__ __align__(1024) uint8_t smem_raw[];
  const uint32_t sb = (uint32_t)__cvta_generic_to_shared(smem_raw);
  const uint32_t bar0 = sb + SM_BAR;
  const int tid = threadIdx.x, lane = tid & 31;
  const int warp = __shfl_sync(0xffffffffu, tid >> 5, 0);
  const int cta = blockIdx.x;
  const int rank = cta & 1;
  const int mt = (cta >> 4) * 2 + rank, nt = (cta >> 1) & 7;
#define BAR(i) (bar0 + 8 * (i))

  if (warp >= 16 && elect()) {
    if (warp == 16) {
#pragma unroll
      for (int i = 0; i < 4; i++) { mbar_init(BAR(B_XF + i), 1); mbar_init(BAR(B_AF + i), 1); }
    } else if (warp == 17) {
#pragma unroll
      for (int b = 4; b < 24; b++) if (b < 8 || b >= 12) mbar_init(BAR(b), bar_count(b));
    } else if (warp == 18) {
#pragma unroll
      for (int b = 24; b < 38; b++) mbar_init(BAR(b), bar_count(b));
    } else {
#pragma unroll
      for (int b = 38; b < NBAR; b++) mbar_init(BAR(b), bar_count(b));
      if ((sb & 0xFFFFFFu) != SBC) __trap();
    }
    asm volatile("fence.mbarrier_init.release.cluster;" ::: "memory");
  }
  __syncwarp();
  asm volatile("barrier.cluster.arrive.relaxed.aligned;" ::: "memory");
  if (warp == 16 && elect()) {
#pragma unroll
    for (int i = 0; i < 1; i++) {
      mbar_expect(BAR(B_AF + i), 24576);
      tma3d(sb + SM_R + i * 24576, &tm_wqkv, nt * 64, i * 64, 0, BAR(B_AF + i));
      mbar_expect(BAR(B_XF + i), 16384);
      tma2d(sb + i * 16384, &tm_x, i * 64, mt * 128, BAR(B_XF + i));
      tma3d(sb + SM_R + i * 24576 + 12288, &tm_wqkv, nt * 64, i * 64 + 32, 0, BAR(B_AF + i));
    }
  }
  __syncwarp();
  asm volatile("barrier.cluster.wait.acquire.aligned;" ::: "memory");
  auto wq_issue = [&](int i) {
    const int s = i & 3;
    mbar_expect(BAR(B_AF + s), 24576);
    tma3d_mc(sb + SM_R + s * 24576 + rank * 12288, &tm_wqkv, nt * 64, i * 64 + rank * 32, 0, BAR(B_AF + s));
  };
  auto x_issue = [&](int i) {
    mbar_expect(BAR(B_XF + i), i == 7 ? 16384 + 448 + 128 : 16384);
    tma2d(xslab(sb, i), &tm_x, i * 64, mt * 128, BAR(B_XF + i));
  };
  if (warp == 16 && elect()) {
#pragma unroll
    for (int i = 1; i < 4; i++) { wq_issue(i); x_issue(i); }
#pragma unroll
    for (int i = 4; i < 5; i++) x_issue(i);
  }

  if (warp >= 16) {
    const int w4 = warp - 16;
    asm volatile("setmaxnreg.dec.sync.aligned.u32 32;");
    auto ffn2_issue = [&](int n) {
      const int s = n & 1;
      mbar_expect(BAR(B_CF + s), 49152);
      bulk1d(sb + SM_R + s * 49152, g_h + (mt * 14 + n) * 32768, 32768, BAR(B_CF + s));
      tma2d(sb + SM_R + s * 49152 + 32768, &tm_w2, nt * 64, n * 128, BAR(B_CF + s));
    };
    uint32_t ep = 0;
    if (w4 == 0) {
      if (elect()) {
        bulk1d(sb + SM_B1, prm.b1 + nt * 224, 448, BAR(B_XF + 7));
        bulk1d(sb + SM_GW, prm.gate_w + nt * 64, 128, BAR(B_XF + 7));
        ep = ldcg32(&g_epoch[cta]) + 1;
        asm volatile("prefetch.tensormap [%0];" ::"l"(&tm_w1a) : "memory");
        asm volatile("prefetch.tensormap [%0];" ::"l"(&tm_w1b) : "memory");
#pragma unroll
        for (int i = 4; i < 8; i++) {
          mbar_wait(BAR(B_AE + i - 4), 0);
          wq_issue(i);
          if (i + 1 < 8) x_issue(i + 1);
          if (i == 4) l2_prefetch((const uint8_t*)prm.w1 + cta * 14336, 14336);
        }
        auto w1_issue = [&](int n) {
          const int s = n % 6;
          if (n < 8) {
            mbar_expect(BAR(B_BF + s), 16384);
            tma3d_mc(sb + SM_R + s * 16384 + rank * 8192, &tm_w1a, 0, n * 64 + rank * 32, nt * 7, BAR(B_BF + s));
          } else {
            mbar_expect(BAR(B_B2F + s), 12288);
            tma3d_mc(sb + SM_R + s * 16384 + rank * 8192, &tm_w1b, 0, f1_order(n - 8) * 64 + rank * 32, nt * 7 + 4, BAR(B_B2F + s));
          }
        };
#pragma unroll
        for (int n = 0; n < 16; n++) {
          if (n < 6) mbar_wait(BAR(B_AE + (n * 2 + 1) / 3), 1);
          else mbar_wait(BAR(B_BE + n % 6), (n / 6 - 1) & 1);
          w1_issue(n);
        }
        mbar_wait(BAR(B_GATE), 0);
        fence_async_gmem();
#pragma unroll
        for (int i = 0; i < 8; i++) {
          if (i == 2) mbar_wait(BAR(B_BE + 3), 0);
          const int s = f1_order(i);
          if (i == 0) mbar_expect(BAR(B_XF), 2 * 16384);
          if (i == 2) mbar_expect(BAR(B_XF + 1), 6 * 16384);
          bulk1d_mc(xslab(sb, s) + rank * 8192, g_kv + (cta >> 2) * 131072 + s * 16384 + rank * 8192, 8192, BAR(B_XF + (i >= 2)));
        }
        cnt_wait(&g_cnt[(8 + mt) * 32], ep * CNT_H);
        fence_async_gmem();
        ffn2_issue(0);
        ffn2_issue(1);
      }
    } else if (w4 == 1) {
      ep = ldcg32(&g_epoch[cta]) + 1;
#pragma unroll
      for (int i = 0; i < 8; i++)
        sts32(sb + SM_ONES + i * 128 + lane * 4, i < 4 ? 0x39B539B5u : 0x3F803F80u);
      fence_async_smem();
      const int hn = cta >> 4, qb = cta & 3;
      mbar_wait(BAR(B_SQ), 0);
      cnt_wait(&g_cnt[hn * 32], ep * CNT_QKV);
      const uint32_t* st = g_stat + hn * 384;
      uint32_t sq = ldcg32(st + qb * 32 + lane), sk = 0, sv = 0;
#pragma unroll
      for (int i = 0; i < 4; i++) { sk = max(sk, ldcg32(st + 128 + i * 32 + lane)); sv = max(sv, ldcg32(st + 256 + i * 32 + lane)); }
      sq = __reduce_max_sync(0xffffffffu, sq);
      sk = __reduce_max_sync(0xffffffffu, sk);
      sv = __reduce_max_sync(0xffffffffu, sv);
      __syncwarp();
      if (lane == 0) {
        const float fq = __uint_as_float(sq), fk = __uint_as_float(sk), fv = __uint_as_float(sv);
        const bool safe = (fq * fk <= 1590.f) && (fq <= 1048576.f) && (fk <= 1048576.f) && (fv <= 1.0e12f) && (fv >= 1.0e-12f);
        sts32(sb + SM_FLAG, safe ? 1u : 0u);
        sts32(sb + SM_FLAG + 16, 0x37503750u); sts32(sb + SM_FLAG + 20, 0x37503750u); sts32(sb + SM_FLAG + 24, 0xC060C060u); sts32(sb + SM_FLAG + 28, 0xC060C060u);
        mbar_arrive(BAR(B_GATE));
      }
    } else if (w4 == 2) {
      if (elect()) {
        mbar_wait(BAR(B_SQ), 0);
        cnt_bump(&g_cnt[nt * 32]);
        l2_prefetch((const uint8_t*)prm.w2 + cta * 14336, 14336);
        l2_prefetch((const uint8_t*)prm.wo + cta * 4096, 4096);
        mbar_wait(BAR(B_SH), 0);
        asm volatile("cp.async.bulk.global.shared::cta.bulk_group [%0], [%1], %2;" ::"l"(g_h + (mt * 56 + nt * 7) * 8192), "r"(sb + SM_R + 65536), "r"(32768) : "memory");
        asm volatile("cp.async.bulk.global.shared::cta.bulk_group [%0], [%1], %2;" ::"l"(g_h + (mt * 56 + nt * 7 + 4) * 8192), "r"(sb + SM_R), "r"(24576) : "memory");
        asm volatile("cp.async.bulk.commit_group;" ::: "memory");
        asm volatile("cp.async.bulk.wait_group 0;" ::: "memory");
        cnt_bump(&g_cnt[(8 + mt) * 32]);
      }
    }
    named_sync(5, 128);
    asm volatile("setmaxnreg.inc.sync.aligned.u32 96;");
    fence_async_gmem();
    ep = __reduce_max_sync(0xffffffffu, ep);
    float acc[64];
    float (&acc0)[32] = *reinterpret_cast<float (*)[32]>(&acc[0]);
    float (&acc1)[32] = *reinterpret_cast<float (*)[32]>(&acc[32]);
    {
      const float b0 = 2.0f * __bfloat162float(prm.b2[nt * 64 + w4 * 16 + (lane >> 2)]);
      const float b1 = 2.0f * __bfloat162float(prm.b2[nt * 64 + w4 * 16 + (lane >> 2) + 8]);
#pragma unroll
      for (int j = 0; j < 16; j++) { acc[4 * j] = acc[4 * j + 1] = b0; acc[4 * j + 2] = acc[4 * j + 3] = b1; }
    }
    fop(acc);
    {
      const uint32_t zero = __shfl_sync(0xffffffffu, sb >> 30, 0);
      const uint64_t dA0 = mk64((((SBC + SM_R + 32768) >> 4) | (1u << 16)) + zero, 0x40000040u + zero);
      const uint64_t dB0 = mk64((((SBC + SM_R) >> 4) | (8u << 16)) + zero, 32u + zero);
#pragma unroll 1
      for (int n2 = 0; n2 < 7; n2++) {
        const uint32_t par = n2 & 1;
        const int issuer = n2 < 6 ? w4 - 2 * (n2 & 1) : -1;
#pragma unroll
        for (int s = 0; s < 2; s++) {
          mbar_wait(BAR(B_CF + s), par);
#pragma unroll
          for (int k = 0; k < 8; k++) {
            wg_fence();
            wgmma_ss_n128_f32_bf16<1, 0>(acc, dA0 + s * 3072 + k * 128, dB0 + s * 3072 + (k >> 1) * 512 + (k & 1) * 16, 1);
            wg_commit();
            wg_wait<0>();
          }
          named_sync(5, 128);
          if (issuer == s && elect()) ffn2_issue(n2 * 2 + 2 + s);
          __syncwarp();
        }
      }
    }
    auto o0_issue = [&](int n) {
      const int s = n & 3;
      mbar_expect(BAR(B_OF + s), 8192);
      bulk1d(sb + SM_R + 65536 + s * 8192, g_o + mt * 65536 + n * 8192, 8192, BAR(B_OF + s));
    };
    float ez;
    {
      const float* gp = g_gl + mt * 1024 + (tid & 127);
      float z = 0.f;
#pragma unroll
      for (int i = 0; i < 8; i++) z += __uint_as_float(ldcg32(gp + i * 128));
      ez = __expf(-clampz(z));
      sts32(sb + SM_GW + (tid & 127) * 4, __float_as_uint(0.5f * ez));
    }
    if (w4 == 0 && elect()) {
      mbar_expect(BAR(B_WO), 65536);
#pragma unroll
      for (int n = 0; n < 8; n++) tma5d(sb + SM_R + n * 8192, &tm_wo, nt * 64, n * 4, BAR(B_WO));
      mbar_wait(BAR(B_P1), 0);
      cnt_bump(&g_cnt[(24 + (cta & 3)) * 32]);
      cnt_wait(&g_cnt[(24 + (mt >> 2)) * 32], ep * CNT_O);
      fence_async_gmem();
#pragma unroll
      for (int n = 0; n < 4; n++) o0_issue(n);
    }
    named_sync(5, 128);
    fop(acc);
#pragma unroll
    for (int j = 0; j < 16; j++) {
      const float2 e = lds64f(sb + SM_GW + (j * 8 + (lane & 3) * 2) * 4);
      acc[4 * j] *= e.x; acc[4 * j + 1] *= e.y; acc[4 * j + 2] *= e.x; acc[4 * j + 3] *= e.y;
    }
    fop(acc);
    mbar_wait(BAR(B_WO), 0);
    uint8_t* outp = (uint8_t*)prm.out + (size_t)(mt * 128) * 1024 + nt * 128 + w4 * 32;
#pragma unroll
    for (int n = 0; n < 8; n++) {
      const int s = n & 3;
      mbar_wait(BAR(B_OF + s), (n >> 2) & 1);
      const uint64_t dA = mkdesc(SBC + SM_R + n * 8192, 16, 1024, 1);
      const uint64_t dB = mkdesc(SBC + SM_R + 65536 + s * 8192, 128, 1024, 0);
      wg_fence();
#pragma unroll
      for (int k = 0; k < 4; k++) wgmma_ss_n64_f32_bf16<1, 0>(acc0, dA + k * 128, dB + k * 16, 1);
      wg_commit();
      wg_wait<0>();
      if (n < 5) named_sync(5, 128);
      if (n == 0) sts32(sb + SM_GW + (tid & 127) * 4, __float_as_uint(rcp(1.0f + ez)));
      if (n < 4) {
        if (w4 == 0 && elect()) o0_issue(n + 4);
        __syncwarp();
      }
    }
    fop(acc0);
    out_store(acc0, sb + SM_GW, sb + SM_R + 65536 + w4 * 2048, outp, lane);
    if (lane == 0) mbar_arrive(BAR(B_M0));
    if (w4 == 0 && elect()) {
      g_epoch[cta] = ep;
      mbar_wait(BAR(B_T + 3), 0);
    }
    named_sync(5, 128);
#pragma unroll
    for (int i = 0; i < 8; i++) {
      const int n = 7 - i;
      if ((i & 1) == 0) mbar_wait(BAR(B_T + (n >> 1)), 0);
      const uint64_t dA = mkdesc(SBC + SM_R + (n & 1) * 8192, 16, 1024, 1) + (uint64_t)(((mt - (n >> 1)) & 3) * 1024);
      const uint64_t dB = mkdesc(SBC + (n < 4 ? SM_K : SM_R + 32768) + n * 8192, 128, 1024, 0);
      wg_fence();
#pragma unroll
      for (int k = 0; k < 4; k++) wgmma_ss_n64_f32_bf16<1, 0>(acc1, dA + k * 128, dB + k * 16, 1);
      wg_commit();
    }
    wg_wait<0>();
    fop(acc1);
    out_store(acc1, sb + SM_GW + 256, sb + SM_K + 32768 + w4 * 2048, outp + 65536, lane);
  } else {
    const int wg = warp >> 2, w4 = warp & 3;
    const int mh = wg & 1;
    const int j16 = mt * 8 + mh * 4 + w4;
    uint32_t* st = g_stat + nt * 384 + j16;
    const uint32_t stage_dst = sb + SM_R + (mh * 8 + w4 * 2 + ((lane >> 3) & 1)) * 512 + (lane >> 4) * 128 + (lane & 7) * 16;
    const int head = cta >> 2;
    const int qt0 = (cta & 3) * 8 + ((wg + (head >> 3)) & 3) * 2;
    uint32_t q0[4], qn[4];
    auto load_q = [&]() {
      mbar_wait(BAR(B_GATE), 0);
      const uint8_t* qp = g_q16 + head * 65536 + (qt0 * 4 + w4) * 512 + (lane >> 2) * 32 + (lane & 3) * 4;
      q0[0] = ldcg32(qp); q0[1] = ldcg32(qp + 256); q0[2] = ldcg32(qp + 16); q0[3] = ldcg32(qp + 272);
      qn[0] = ldcg32(qp + 2048); qn[1] = ldcg32(qp + 2304); qn[2] = ldcg32(qp + 2064); qn[3] = ldcg32(qp + 2320);
    };
    auto qkv_wait = [&](int i) {
      mbar_spin(BAR(B_XF + i), 0);
      mbar_spin(BAR(B_AF + (i & 3)), i >> 2);

    };
    if (wg < 2) {
      asm volatile("setmaxnreg.inc.sync.aligned.u32 128;");
      {
        float acc[64], aq[32];
#pragma unroll
        for (int i = 0; i < 64; i++) acc[i] = 0.f;
#pragma unroll
        for (int i = 0; i < 32; i++) aq[i] = 0.f;
        fop(acc); fop(aq);
        const uint32_t mo = __shfl_sync(0xffffffffu, (tid >> 7 & 1) * 512, 0);
#pragma unroll
        for (int i = 0; i < 8; i++) {
          const int s = i & 3;
          qkv_wait(i);
          const uint64_t dA = mkdesc(xslab(SBC, i), 16, 1024, 1) + (uint64_t)mo;
          const uint64_t dB = mkdesc(SBC + SM_R + s * 24576, 4096, 1024, 1);
          wg_fence();
#pragma unroll
          for (int k = 0; k < 4; k++) {
            wgmma_ss_n128_f32_bf16<0, 1>(acc, dA + k * 2, dB + 256 + (k >> 1) * 768 + (k & 1) * 128, 1);
            wgmma_ss_n64_f32_bf16<0, 1>(aq, dA + k * 2, dB + (k >> 1) * 768 + (k & 1) * 128, 1);
          }
          wg_commit();
          if (i == 6) named_arrive(2, 512);
          wg_wait<1>();
          if (i > 0) mbar_arrive_pair(BAR(B_AE + ((i - 1) & 3)), lane);
        }
        wg_wait<0>();
        mbar_arrive_pair(BAR(B_AE + 3), lane);
        fop(acc); fop(aq);
        uint8_t* kp = g_kv + nt * 4 * 131072 + j16 * 512 + ((lane * 8) ^ (lane & 16));
        uint8_t* qp = g_q16 + nt * 4 * 65536 + j16 * 512 + lane * 8;
        uint32_t qm = 0, km = 0, vm = 0;
        const bool m0 = is_mufu(j16, 0), m1 = is_mufu(j16, 1);
        const float v0 = m0 ? VSCALE : 1.f, v1 = m1 ? VSCALE : 1.f;
        uint32_t pk[48];
#pragma unroll
        for (int hh = 0; hh < 4; hh++) {
          km = max(km, qk_pack<false>(acc + hh * 8, pk + hh * 12, m0 ? 1.f : KSCALE, m1 ? 1.f : KSCALE));
          const float* d = acc + 32 + hh * 8;
          pk[hh * 12 + 4] = packbf(d[0] * v0, d[1] * v0);
          pk[hh * 12 + 5] = packbf(d[2] * v1, d[3] * v1);
          pk[hh * 12 + 6] = packbf(d[4] * v0, d[5] * v0);
          pk[hh * 12 + 7] = packbf(d[6] * v1, d[7] * v1);
#pragma unroll
          for (int i = 0; i < 8; i++) vm = max(vm, __float_as_uint(d[i]) & 0x7FFFFFFFu);
          qm = max(qm, qk_pack<true>(aq + hh * 8, pk + hh * 12 + 8, 1.f, 1.f));
        }
        fop(pk);
#pragma unroll
        for (int hh = 0; hh < 4; hh++) {
          row_store(kp + hh * 131072, pk + hh * 12);
          row_store(kp + hh * 131072 + 65536, pk + hh * 12 + 4);
          row_store(qp + hh * 65536, pk + hh * 12 + 8);
        }
        qm = __reduce_max_sync(0xffffffffu, qm);
        km = __reduce_max_sync(0xffffffffu, km);
        vm = __reduce_max_sync(0xffffffffu, vm);
        if (lane == 0) { st[0] = qm; st[128] = km; st[256] = vm; }
        __syncwarp();
        if (lane == 0) mbar_arrive(BAR(B_SQ));
      }
      named_sync(4, 256);
      asm volatile("setmaxnreg.dec.sync.aligned.u32 96;");
      float acc[48];
      bias_init(acc, sb + SM_B1 + 256, lane);
      fop(acc);
      named_sync(7, 512);
#pragma unroll
      for (int n = 8; n < 16; n++) {
        mbar_wait(BAR(B_B2F + n % 6), n >= 14);
        const uint64_t dA = mkdesc(xslab(SBC, f1_order(n - 8)), 16, 1024, 1) + (uint64_t)(mh * 512);
        const uint64_t dB = mkdesc(SBC + SM_R + (n % 6) * 16384, 2048, 512, 2);
        wg_fence();
#pragma unroll
        for (int k = 0; k < 4; k++) wgmma_ss_n96_f32_bf16<0, 1>(acc, dA + k * 2, dB + (k >> 1) * 512 + (k & 1) * 64, 1);
        wg_commit();
        wg_wait<1>();
        if (n > 8) mbar_arrive_pair(BAR(B_BE + (n - 1) % 6), lane);
        if (n == 12) named_arrive(6, 512);
      }
      wg_wait<0>();
      mbar_arrive_pair(BAR(B_BE + 3), lane);
      fop(acc);
      named_sync(4, 256);
      load_q();
      uint32_t r[24];
      gelu_pack(acc, r);
      h_stage(r, stage_dst);
    } else {
      {
#pragma unroll
        for (int i = 0; i < 8; i++) mbar_wait(BAR(B_XF + i), 0);
        float gl[4] = {0.f, 0.f, 0.f, 0.f};
        fop(gl);
        wg_fence();
        const uint64_t dA = mkdesc(xslab(SBC, nt) + mh * 8192, 16, 1024, 1);
        const uint64_t dG = mkdesc(SBC + SM_GW, 16, 128, 0);
#pragma unroll
        for (int k = 0; k < 4; k++) wgmma_ss_n8_f32_bf16<0, 0>(gl, dA + k * 2, dG + k * 2, 1);
        wg_commit();
        wg_wait<0>();
        fop(gl);
        if ((lane & 3) == 0) {
          float* gp = g_gl + (mt * 8 + nt) * 128 + mh * 64 + w4 * 16 + (lane >> 2);
          gp[0] = gl[0];
          gp[8] = gl[2];
        }
        __syncwarp();
        if (lane == 0) mbar_arrive(BAR(B_SQ));
      }
      uint32_t r[32];
      {
        float acc[64];
        bias_init(acc, sb + SM_B1, lane);
        fop(acc);
        named_sync(2, 512);
#pragma unroll
        for (int n = 0; n < 8; n++) {
          mbar_wait(BAR(B_BF + n % 6), n >= 6);
          const uint64_t dA = mkdesc(SBC, 16, 1024, 1) + (uint64_t)(mh * 512 + n * 1024);
          const uint64_t dB = mkdesc(SBC + SM_R + (n % 6) * 16384, 2048, 512, 2);
          wg_fence();
#pragma unroll
          for (int k = 0; k < 4; k++) wgmma_ss_n128_f32_bf16<0, 1>(acc, dA + k * 2, dB + (k >> 1) * 512 + (k & 1) * 64, 1);
          wg_commit();
          if (n == 7) named_arrive(7, 512);
          wg_wait<1>();
          if (n > 0) mbar_arrive_pair(BAR(B_BE + (n - 1) % 6), lane);
        }
        wg_wait<0>();
        mbar_arrive_pair(BAR(B_BE + 1), lane);
        fop(acc);
        gelu_pack(acc, r);
        fop(r);
      }
      load_q();
      named_sync(6, 512);
      h_stage(r, stage_dst + 65536);
    }
    fence_async_smem();
    __syncwarp();
    if (lane == 0) mbar_arrive(BAR(B_SH));

    const uint32_t safe = lds32(sb + SM_FLAG);
    auto finish = [&](const float (&O)[12], int pass) {
      const float s0 = rcp(O[8]), s1 = rcp(O[10]);
      const uint32_t a0 = packbf(O[0] * s0, O[1] * s0), a1 = packbf(O[2] * s1, O[3] * s1);
      const uint32_t a2 = packbf(O[4] * s0, O[5] * s0), a3 = packbf(O[6] * s1, O[7] * s1);
      uint8_t* o1 = g_o1 + (qt0 >> 1) * 65536 + head * 2048 + (tid & 127) * 16;
      if (pass == 0) {
        uint8_t* op = g_o + (qt0 >> 1) * 65536 + (head >> 2) * 8192 + w4 * 2048 + (head & 3) * 256 + lane * 4;
        stg32(op, a0); stg32(op + 1024, a1); stg32(op + 128, a2); stg32(op + 1152, a3);
        *(uint4*)o1 = make_uint4(0, 0, 0, 0);
        __syncwarp();
        if (lane == 0) mbar_arrive(BAR(B_P1));
      } else {
        asm volatile("st.relaxed.gpu.global.v4.u32 [%0], {%1,%2,%3,%4};" ::"l"(o1), "r"(~a0), "r"(~a1), "r"(~a2), "r"(~a3) : "memory");
      }
    };
    if (safe) {
      uint32_t q[4];
#pragma unroll
      for (int i = 0; i < 4; i++) q[i] = q0[i] * safe;
      float O[12];
#pragma unroll
      for (int i = 0; i < 12; i++) O[i] = 0.f;
      fop(O);
      mbar_wait(BAR(B_XF), 1);
      uint32_t P[STEP / 4];
      uint32_t cc[4];
      asm volatile("ld.shared.v4.u32 {%0,%1,%2,%3}, [%4];" : "=r"(cc[0]), "=r"(cc[1]), "=r"(cc[2]), "=r"(cc[3]) : "r"(sb + SM_FLAG + 16) : "memory");
      constexpr int64_t KNEXT = 2 * STEP - (int64_t)((SM_V - SM_K) >> 4);
      auto run = [&](int j0, int j1, auto SECOND) {
        uint32_t lo = v_lo(j0 * NG);
#pragma unroll 1
        do {
          att_step<NM, NP, NG, 0, true, SECOND.value ? SEED2 : SEED1, SECOND.value ? CM2 : CM1>(O, P, q, mk64(lo, KV_HI), KNEXT, cc);
          asm volatile("add.u32 %0, %0, %1;" : "+r"(lo) : "n"(v_lo(NG) - v_lo(0)));
        } while (lo != v_lo(j1 * NG));
        fop(O); fop(q);
      };
      auto last = [&](auto NEXT) {
        constexpr int JL = (REM ? NFULL : NFULL - 1) * NG;
        if constexpr (REM != 0) {
          att_step<NM - 16, NP - 16, NG, 0>(O, P, q, mk64(v_lo((NFULL - 1) * NG), KV_HI), KNEXT, cc);
        }
        if (NEXT.value) {
#pragma unroll
          for (int i = 0; i < 4; i++) q[i] = qn[i] * safe;
          fop(q);
        }
        att_step<NEXT.value ? NM : 0, NP, REM ? NG - 2 : NG, JL>(O, P, q, mk64(v_lo(JL), KV_HI), KNEXT - 2 * STEP - JL * 32, cc);
        fop(O);
      };
      att_step<NM, NP, 0, 0>(O, P, q, mk64(v_lo(0), KV_HI), KNEXT - 2 * STEP, cc);
      run(0, 512 / STEP - 1, BoolC<false>{});
      mbar_wait(BAR(B_XF + 1), 1);
      run(512 / STEP - 1, NFULL - 1, BoolC<false>{});

      last(BoolC<true>{});
      finish(O, 0);
#pragma unroll
      for (int i = 0; i < 12; i++) O[i] = 0.f;
      fop(O);
      run(0, NFULL - 1, BoolC<true>{});
      last(BoolC<false>{});
      if (lane == 0) mbar_arrive(BAR(B_ATT));
      finish(O, 1);
    } else {
      slow_k(sb, prm, head);
#pragma unroll 1
      for (int pass = 0; pass < 2; pass++) {
        float O[12];
        attn_slow(sb, prm, head, (qt0 + pass) * 64 + w4 * 16 + (lane >> 2), O);
        if (pass == 1 && lane == 0) mbar_arrive(BAR(B_ATT));
        finish(O, pass);
      }
    }
    {
      const uint8_t* src = g_o1 + mt * 65536 + ((mt - wg) & 3) * 16384 + (tid & 127) * 16;
      const uint32_t dst = sb + (wg < 2 ? SM_K : SM_R + 32768) + wg * 16384 + (w4 * 2 + ((lane >> 3) & 1)) * 1024 + (lane >> 4) * 128 + (lane & 7) * 16;
      uint4 v[8];
      uint32_t ok[8];
#pragma unroll
      for (int i = 0; i < 8; i++) ok[i] = 0;
      mbar_wait(BAR(B_M0), 0);
      uint32_t spins = 0;
      while (true) {
#pragma unroll
        for (int i = 0; i < 8; i++)
          if (ok[i] == 0)
            asm volatile("ld.relaxed.gpu.global.v4.u32 {%0,%1,%2,%3}, [%4];" : "=r"(v[i].x), "=r"(v[i].y), "=r"(v[i].z), "=r"(v[i].w) : "l"(src + i * 2048) : "memory");
        uint32_t all = 0xFFFFFFFFu;
#pragma unroll
        for (int i = 0; i < 8; i++) { ok[i] = min(min(v[i].x, v[i].y), min(v[i].z, v[i].w)); all = min(all, ok[i]); }
        if (all != 0) break;
        if (++spins > (1u << 21)) __trap();
      }
      __syncwarp();
      if (wg < 2) mbar_spin(BAR(B_ATT), 0);
#pragma unroll
      for (int i = 0; i < 8; i++)
        asm volatile("stmatrix.sync.aligned.m8n8.x4.shared.b16 [%0], {%1,%2,%3,%4};" ::"r"(dst + (i >> 2) * 8192 + (i & 3) * 256),
                     "r"(~v[i].x), "r"(~v[i].y), "r"(~v[i].z), "r"(~v[i].w) : "memory");
      fence_async_smem();
      __syncwarp();
      if (lane == 0) mbar_arrive(BAR(B_T + wg));
    }
  }
#undef BAR
}

typedef CUresult (*EncodeFn)(CUtensorMap*, CUtensorMapDataType, cuuint32_t, void*, const cuuint64_t*, const cuuint64_t*,
                             const cuuint32_t*, const cuuint32_t*, CUtensorMapInterleave, CUtensorMapSwizzle,
                             CUtensorMapL2promotion, CUtensorMapFloatOOBfill);

void make_map(EncodeFn enc, CUtensorMap* m, const void* ptr, int rank, const cuuint64_t* dims, const cuuint64_t* strides,
              const cuuint32_t* box, CUtensorMapSwizzle sw) {
  cuuint32_t es[5] = {1, 1, 1, 1, 1};
  enc(m, CU_TENSOR_MAP_DATA_TYPE_BFLOAT16, rank, const_cast<void*>(ptr), dims, strides, box, es, CU_TENSOR_MAP_INTERLEAVE_NONE, sw,
      CU_TENSOR_MAP_L2_PROMOTION_L2_128B, CU_TENSOR_MAP_FLOAT_OOB_FILL_NONE);
}

}

extern "C" void kernel_launch(void* const* d_in, const int* in_sizes, int n_in, void* d_out, int out_size) {
  (void)in_sizes; (void)n_in; (void)out_size;
  static EncodeFn enc = nullptr;
  if (!enc) {
    void* fn = nullptr;
    cudaDriverEntryPointQueryResult qr;
    cudaGetDriverEntryPoint("cuTensorMapEncodeTiled", &fn, cudaEnableDefault, &qr);
    enc = (EncodeFn)fn;
    cudaFuncSetAttribute(fused_kernel, cudaFuncAttributeMaxDynamicSharedMemorySize, SM_TOTAL);
  }
  CUtensorMap tm_x, tm_wqkv, tm_w1a, tm_w1b, tm_w2, tm_wo;
  {
    cuuint64_t d[2] = {512, 2048}, s[1] = {1024}; cuuint32_t b[2] = {64, 128};
    make_map(enc, &tm_x, d_in[0], 2, d, s, b, CU_TENSOR_MAP_SWIZZLE_128B);
  }
  {
    cuuint64_t d[3] = {512, 512, 3}, s[2] = {3072, 1024}; cuuint32_t b[3] = {64, 32, 3};
    make_map(enc, &tm_wqkv, d_in[1], 3, d, s, b, CU_TENSOR_MAP_SWIZZLE_128B);
  }
  {
    cuuint64_t d[3] = {32, 512, 56}, s[2] = {3584, 64}; cuuint32_t b4[3] = {32, 32, 4}, b3[3] = {32, 32, 3};
    make_map(enc, &tm_w1a, d_in[4], 3, d, s, b4, CU_TENSOR_MAP_SWIZZLE_64B);
    make_map(enc, &tm_w1b, d_in[4], 3, d, s, b3, CU_TENSOR_MAP_SWIZZLE_64B);
  }
  {
    cuuint64_t d[2] = {512, 1792}, s[1] = {1024}; cuuint32_t b[2] = {64, 128};
    make_map(enc, &tm_w2, d_in[6], 2, d, s, b, CU_TENSOR_MAP_SWIZZLE_128B);
  }
  {
    cuuint64_t d[5] = {512, 2, 2, 4, 32}, s[4] = {1024, 8192, 2048, 16384}; cuuint32_t b[5] = {64, 2, 2, 4, 4};
    make_map(enc, &tm_wo, d_in[2], 5, d, s, b, CU_TENSOR_MAP_SWIZZLE_128B);
  }
  Params prm;
  prm.x = (const __nv_bfloat16*)d_in[0];
  prm.wqkv = (const __nv_bfloat16*)d_in[1];
  prm.wo = (const __nv_bfloat16*)d_in[2];
  prm.w1 = (const __nv_bfloat16*)d_in[4];
  prm.w2 = (const __nv_bfloat16*)d_in[6];
  prm.b1 = (const __nv_bfloat16*)d_in[5];
  prm.b2 = (const __nv_bfloat16*)d_in[7];
  prm.gate_w = (const __nv_bfloat16*)d_in[8];
  prm.out = (__nv_bfloat16*)d_out;
  fused_kernel<<<NCTA, NTHREADS, SM_TOTAL>>>(tm_x, tm_wqkv, tm_w1a, tm_w1b, tm_w2, tm_wo, prm);
}
```
